```python
import torch

def _softmax(x, axis=-1):
    return torch.softmax(x, dim=axis)
def _gelu(x):
    return torch.nn.functional.gelu(x, approximate="tanh")
def _silu(x):
    return torch.nn.functional.silu(x)
def _sigmoid(x):
    return torch.sigmoid(x)
def _layernorm(x, axis=-1, eps=1e-5):
    m = x.mean(dim=axis, keepdim=True)
    v = x.var(dim=axis, keepdim=True, unbiased=False)
    return (x - m) / torch.sqrt(v + eps)
def _scatter_add(tgt, idx, src, axis=0):
    return tgt.clone().index_add_(axis, idx, src)
def _segment_sum(src, seg, n):
    out = torch.zeros((n,) + src.shape[1:], dtype=src.dtype)
    return out.index_add_(0, seg, src)
def _pad(x, pw):
    flat = tuple(v for pair in reversed(pw) for v in pair)
    return torch.nn.functional.pad(x, flat)

kernel_name = 'interleave_layers__linear_attn_block__grouped_kv_mqa__prompt'

def setup_inputs():

    _w = (lambda a: (lambda t: t.to(torch.bfloat16) if t.is_floating_point() else t)(torch.as_tensor(a)))
    def _A_setup():
        B, S, D = 1, 2048, 512
        return {
            "x": _w((lambda *s: torch.randn(*s, dtype=torch.bfloat16) * 0.05)(B, S, D)),
            "wqkv": _w((lambda *s: torch.randn(*s, dtype=torch.bfloat16) * 0.05)(D, 3 * D)),
            "wo": _w((lambda *s: torch.randn(*s, dtype=torch.bfloat16) * 0.05)(D, D)),
        }
    _A_in = _A_setup()

    def _B_setup():
        B, S, D, H = 1, 2048, 512, 32
        Dh = D // H
        return {
            "x": _w((lambda *s: torch.randn(*s, dtype=torch.bfloat16) * 0.05)(B, S, D)),
            "wq": _w((lambda *s: torch.randn(*s, dtype=torch.bfloat16) * 0.1)(D, H * Dh)),
            "wk": _w((lambda *s: torch.randn(*s, dtype=torch.bfloat16) * 0.1)(D, Dh)),
            "wv": _w((lambda *s: torch.randn(*s, dtype=torch.bfloat16) * 0.05)(D, Dh)),
            "wo": _w((lambda *s: torch.randn(*s, dtype=torch.bfloat16) * 0.05)(H * Dh, D)),
        }
    _B_in = _B_setup()

    return {
        "A_x": _A_in["x"],
        "A_wqkv": _A_in["wqkv"],
        "A_wo": _A_in["wo"],
        "B_x": _B_in["x"],
        "B_wq": _B_in["wq"],
        "B_wk": _B_in["wk"],
        "B_wv": _B_in["wv"],
        "B_wo": _B_in["wo"],
    }

def reference(A_x, A_wqkv, A_wo, B_x, B_wq, B_wk, B_wv, B_wo):
    def _A_ref(x, wqkv, wo):
        B, S, D = x.shape
        H = 32; Dh = D // H
        qkv = (lambda x, *d: x.permute(*d))((x @ wqkv).reshape(B, S, 3, H, Dh), 2, 0, 3, 1, 4)
        q, k, v = qkv[0], qkv[1], qkv[2]
        phi = lambda t: torch.where(t > 0, t + 1, torch.exp(t)) + 1e-6
        pq, pk = phi(q), phi(k)
        kv = torch.einsum("bhsd,bhse->bhde", pk, v)
        z = torch.einsum("bhsd->bhd", pk)
        num = torch.einsum("bhqd,bhde->bhqe", pq, kv)
        den = torch.einsum("bhqd,bhd->bhq", pq, z)[..., None] + 1e-6
        o = num / den
        return (lambda x, *d: x.permute(*d))(o, 0, 2, 1, 3).reshape(B, S, D) @ wo

    def _B_ref(x, wq, wk, wv, wo):
        B, S, D = x.shape
        H = 32
        Dh = D // H
        q = (lambda x, *d: x.permute(*d))((x @ wq).reshape(B, S, H, Dh), 0, 2, 1, 3)
        k = x @ wk
        v = x @ wv
        scores = torch.einsum("bhqd,bkd->bhqk", q, k) * (Dh ** -0.5)
        p = _softmax(scores, axis=-1)
        o = torch.einsum("bhqk,bkd->bhqd", p, v)
        return (lambda x, *d: x.permute(*d))(o, 0, 2, 1, 3).reshape(B, S, H * Dh) @ wo

    x = A_x
    x = x + _A_ref(_layernorm(x, axis=-1), A_wqkv, A_wo)
    x = x + _B_ref(_layernorm(x, axis=-1), B_wq, B_wk, B_wv, B_wo)
    x = x + _A_ref(_layernorm(x, axis=-1), A_wqkv, A_wo)
    x = x + _B_ref(_layernorm(x, axis=-1), B_wq, B_wk, B_wv, B_wo)
    return x
```

```cpp
#include <cuda_runtime.h>
#include <cuda_bf16.h>
#include <cuda.h>
#include <stdint.h>

__device__ __forceinline__ void wgmma_ss_n128_tb(float (&d)[64], uint64_t da, uint64_t db, int sd){
  asm volatile("{.reg .pred p; setp.ne.b32 p, %66, 0;\n wgmma.mma_async.sync.aligned.m64n128k16.f32.bf16.bf16 {%0,%1,%2,%3,%4,%5,%6,%7,%8,%9,%10,%11,%12,%13,%14,%15,%16,%17,%18,%19,%20,%21,%22,%23,%24,%25,%26,%27,%28,%29,%30,%31,%32,%33,%34,%35,%36,%37,%38,%39,%40,%41,%42,%43,%44,%45,%46,%47,%48,%49,%50,%51,%52,%53,%54,%55,%56,%57,%58,%59,%60,%61,%62,%63}, %64, %65, p, 1, 1, 0, 1;}\n"
  : "+f"(d[0]),"+f"(d[1]),"+f"(d[2]),"+f"(d[3]),"+f"(d[4]),"+f"(d[5]),"+f"(d[6]),"+f"(d[7]),"+f"(d[8]),"+f"(d[9]),"+f"(d[10]),"+f"(d[11]),"+f"(d[12]),"+f"(d[13]),"+f"(d[14]),"+f"(d[15]),"+f"(d[16]),"+f"(d[17]),"+f"(d[18]),"+f"(d[19]),"+f"(d[20]),"+f"(d[21]),"+f"(d[22]),"+f"(d[23]),"+f"(d[24]),"+f"(d[25]),"+f"(d[26]),"+f"(d[27]),"+f"(d[28]),"+f"(d[29]),"+f"(d[30]),"+f"(d[31]),"+f"(d[32]),"+f"(d[33]),"+f"(d[34]),"+f"(d[35]),"+f"(d[36]),"+f"(d[37]),"+f"(d[38]),"+f"(d[39]),"+f"(d[40]),"+f"(d[41]),"+f"(d[42]),"+f"(d[43]),"+f"(d[44]),"+f"(d[45]),"+f"(d[46]),"+f"(d[47]),"+f"(d[48]),"+f"(d[49]),"+f"(d[50]),"+f"(d[51]),"+f"(d[52]),"+f"(d[53]),"+f"(d[54]),"+f"(d[55]),"+f"(d[56]),"+f"(d[57]),"+f"(d[58]),"+f"(d[59]),"+f"(d[60]),"+f"(d[61]),"+f"(d[62]),"+f"(d[63])
  : "l"(da),"l"(db),"r"(sd));
}
__device__ __forceinline__ void wgmma_ss_n64_tb(float (&d)[32], uint64_t da, uint64_t db, int sd){
  asm volatile("{.reg .pred p; setp.ne.b32 p, %34, 0;\n wgmma.mma_async.sync.aligned.m64n64k16.f32.bf16.bf16 {%0,%1,%2,%3,%4,%5,%6,%7,%8,%9,%10,%11,%12,%13,%14,%15,%16,%17,%18,%19,%20,%21,%22,%23,%24,%25,%26,%27,%28,%29,%30,%31}, %32, %33, p, 1, 1, 0, 1;}\n"
  : "+f"(d[0]),"+f"(d[1]),"+f"(d[2]),"+f"(d[3]),"+f"(d[4]),"+f"(d[5]),"+f"(d[6]),"+f"(d[7]),"+f"(d[8]),"+f"(d[9]),"+f"(d[10]),"+f"(d[11]),"+f"(d[12]),"+f"(d[13]),"+f"(d[14]),"+f"(d[15]),"+f"(d[16]),"+f"(d[17]),"+f"(d[18]),"+f"(d[19]),"+f"(d[20]),"+f"(d[21]),"+f"(d[22]),"+f"(d[23]),"+f"(d[24]),"+f"(d[25]),"+f"(d[26]),"+f"(d[27]),"+f"(d[28]),"+f"(d[29]),"+f"(d[30]),"+f"(d[31])
  : "l"(da),"l"(db),"r"(sd));
}
__device__ __forceinline__ void wgmma_ss_n16_ta(float (&d)[8], uint64_t da, uint64_t db, int sd){
  asm volatile("{.reg .pred p; setp.ne.b32 p, %10, 0;\n wgmma.mma_async.sync.aligned.m64n16k16.f32.bf16.bf16 {%0,%1,%2,%3,%4,%5,%6,%7}, %8, %9, p, 1, 1, 1, 0;}\n"
  : "+f"(d[0]),"+f"(d[1]),"+f"(d[2]),"+f"(d[3]),"+f"(d[4]),"+f"(d[5]),"+f"(d[6]),"+f"(d[7])
  : "l"(da),"l"(db),"r"(sd));
}
__device__ __forceinline__ void wgmma_rs_n64(float (&d)[32], uint32_t a0, uint32_t a1, uint32_t a2, uint32_t a3, uint64_t db, int sd){
  asm volatile("{.reg .pred p; setp.ne.b32 p, %37, 0;\n wgmma.mma_async.sync.aligned.m64n64k16.f32.bf16.bf16 {%0,%1,%2,%3,%4,%5,%6,%7,%8,%9,%10,%11,%12,%13,%14,%15,%16,%17,%18,%19,%20,%21,%22,%23,%24,%25,%26,%27,%28,%29,%30,%31}, {%32,%33,%34,%35}, %36, p, 1, 1, 0;}\n"
  : "+f"(d[0]),"+f"(d[1]),"+f"(d[2]),"+f"(d[3]),"+f"(d[4]),"+f"(d[5]),"+f"(d[6]),"+f"(d[7]),"+f"(d[8]),"+f"(d[9]),"+f"(d[10]),"+f"(d[11]),"+f"(d[12]),"+f"(d[13]),"+f"(d[14]),"+f"(d[15]),"+f"(d[16]),"+f"(d[17]),"+f"(d[18]),"+f"(d[19]),"+f"(d[20]),"+f"(d[21]),"+f"(d[22]),"+f"(d[23]),"+f"(d[24]),"+f"(d[25]),"+f"(d[26]),"+f"(d[27]),"+f"(d[28]),"+f"(d[29]),"+f"(d[30]),"+f"(d[31])
  : "r"(a0),"r"(a1),"r"(a2),"r"(a3),"l"(db),"r"(sd));
}
__device__ __forceinline__ void wgmma_rs_n24_tb(float (&d)[12], uint32_t a0, uint32_t a1, uint32_t a2, uint32_t a3, uint64_t db, int sd){
  asm volatile("{.reg .pred p; setp.ne.b32 p, %17, 0;\n wgmma.mma_async.sync.aligned.m64n24k16.f32.bf16.bf16 {%0,%1,%2,%3,%4,%5,%6,%7,%8,%9,%10,%11}, {%12,%13,%14,%15}, %16, p, 1, 1, 1;}\n"
  : "+f"(d[0]),"+f"(d[1]),"+f"(d[2]),"+f"(d[3]),"+f"(d[4]),"+f"(d[5]),"+f"(d[6]),"+f"(d[7]),"+f"(d[8]),"+f"(d[9]),"+f"(d[10]),"+f"(d[11])
  : "r"(a0),"r"(a1),"r"(a2),"r"(a3),"l"(db),"r"(sd));
}
__device__ __forceinline__ void wgmma_pv_pb0(float (&d)[12], uint64_t db, int sd){
  asm volatile("{.reg .pred p; setp.ne.b32 p, %13, 0;\n wgmma.mma_async.sync.aligned.m64n24k16.f32.bf16.bf16 {%0,%1,%2,%3,%4,%5,%6,%7,%8,%9,%10,%11}, {pb0,pb1,pb2,pb3}, %12, p, 1, 1, 1;}\n"
  : "+f"(d[0]),"+f"(d[1]),"+f"(d[2]),"+f"(d[3]),"+f"(d[4]),"+f"(d[5]),"+f"(d[6]),"+f"(d[7]),"+f"(d[8]),"+f"(d[9]),"+f"(d[10]),"+f"(d[11])
  : "l"(db),"r"(sd));
}
__device__ __forceinline__ void wgmma_pv_pb1(float (&d)[12], uint64_t db, int sd){
  asm volatile("{.reg .pred p; setp.ne.b32 p, %13, 0;\n wgmma.mma_async.sync.aligned.m64n24k16.f32.bf16.bf16 {%0,%1,%2,%3,%4,%5,%6,%7,%8,%9,%10,%11}, {pb4,pb5,pb6,pb7}, %12, p, 1, 1, 1;}\n"
  : "+f"(d[0]),"+f"(d[1]),"+f"(d[2]),"+f"(d[3]),"+f"(d[4]),"+f"(d[5]),"+f"(d[6]),"+f"(d[7]),"+f"(d[8]),"+f"(d[9]),"+f"(d[10]),"+f"(d[11])
  : "l"(db),"r"(sd));
}
__device__ __forceinline__ void wgmma_pv_pb2(float (&d)[12], uint64_t db, int sd){
  asm volatile("{.reg .pred p; setp.ne.b32 p, %13, 0;\n wgmma.mma_async.sync.aligned.m64n24k16.f32.bf16.bf16 {%0,%1,%2,%3,%4,%5,%6,%7,%8,%9,%10,%11}, {pb8,pb9,pb10,pb11}, %12, p, 1, 1, 1;}\n"
  : "+f"(d[0]),"+f"(d[1]),"+f"(d[2]),"+f"(d[3]),"+f"(d[4]),"+f"(d[5]),"+f"(d[6]),"+f"(d[7]),"+f"(d[8]),"+f"(d[9]),"+f"(d[10]),"+f"(d[11])
  : "l"(db),"r"(sd));
}
__device__ __forceinline__ void wgmma_pv_pb3(float (&d)[12], uint64_t db, int sd){
  asm volatile("{.reg .pred p; setp.ne.b32 p, %13, 0;\n wgmma.mma_async.sync.aligned.m64n24k16.f32.bf16.bf16 {%0,%1,%2,%3,%4,%5,%6,%7,%8,%9,%10,%11}, {pb12,pb13,pb14,pb15}, %12, p, 1, 1, 1;}\n"
  : "+f"(d[0]),"+f"(d[1]),"+f"(d[2]),"+f"(d[3]),"+f"(d[4]),"+f"(d[5]),"+f"(d[6]),"+f"(d[7]),"+f"(d[8]),"+f"(d[9]),"+f"(d[10]),"+f"(d[11])
  : "l"(db),"r"(sd));
}
template<int I> __device__ __forceinline__ void pb_fma(uint32_t y, uint32_t u, uint32_t e);
template<int I> __device__ __forceinline__ void pb_cvt(float lo, float hi);
template<> __device__ __forceinline__ void pb_fma<0>(uint32_t y, uint32_t u, uint32_t e){ asm volatile("fma.rn.bf16x2 pb0, %0, %1, %2;"::"r"(y),"r"(u),"r"(e)); }
template<> __device__ __forceinline__ void pb_cvt<0>(float lo, float hi){ asm volatile("cvt.rn.bf16x2.f32 pb0, %1, %0;"::"f"(lo),"f"(hi)); }
template<> __device__ __forceinline__ void pb_fma<1>(uint32_t y, uint32_t u, uint32_t e){ asm volatile("fma.rn.bf16x2 pb1, %0, %1, %2;"::"r"(y),"r"(u),"r"(e)); }
template<> __device__ __forceinline__ void pb_cvt<1>(float lo, float hi){ asm volatile("cvt.rn.bf16x2.f32 pb1, %1, %0;"::"f"(lo),"f"(hi)); }
template<> __device__ __forceinline__ void pb_fma<2>(uint32_t y, uint32_t u, uint32_t e){ asm volatile("fma.rn.bf16x2 pb2, %0, %1, %2;"::"r"(y),"r"(u),"r"(e)); }
template<> __device__ __forceinline__ void pb_cvt<2>(float lo, float hi){ asm volatile("cvt.rn.bf16x2.f32 pb2, %1, %0;"::"f"(lo),"f"(hi)); }
template<> __device__ __forceinline__ void pb_fma<3>(uint32_t y, uint32_t u, uint32_t e){ asm volatile("fma.rn.bf16x2 pb3, %0, %1, %2;"::"r"(y),"r"(u),"r"(e)); }
template<> __device__ __forceinline__ void pb_cvt<3>(float lo, float hi){ asm volatile("cvt.rn.bf16x2.f32 pb3, %1, %0;"::"f"(lo),"f"(hi)); }
template<> __device__ __forceinline__ void pb_fma<4>(uint32_t y, uint32_t u, uint32_t e){ asm volatile("fma.rn.bf16x2 pb4, %0, %1, %2;"::"r"(y),"r"(u),"r"(e)); }
template<> __device__ __forceinline__ void pb_cvt<4>(float lo, float hi){ asm volatile("cvt.rn.bf16x2.f32 pb4, %1, %0;"::"f"(lo),"f"(hi)); }
template<> __device__ __forceinline__ void pb_fma<5>(uint32_t y, uint32_t u, uint32_t e){ asm volatile("fma.rn.bf16x2 pb5, %0, %1, %2;"::"r"(y),"r"(u),"r"(e)); }
template<> __device__ __forceinline__ void pb_cvt<5>(float lo, float hi){ asm volatile("cvt.rn.bf16x2.f32 pb5, %1, %0;"::"f"(lo),"f"(hi)); }
template<> __device__ __forceinline__ void pb_fma<6>(uint32_t y, uint32_t u, uint32_t e){ asm volatile("fma.rn.bf16x2 pb6, %0, %1, %2;"::"r"(y),"r"(u),"r"(e)); }
template<> __device__ __forceinline__ void pb_cvt<6>(float lo, float hi){ asm volatile("cvt.rn.bf16x2.f32 pb6, %1, %0;"::"f"(lo),"f"(hi)); }
template<> __device__ __forceinline__ void pb_fma<7>(uint32_t y, uint32_t u, uint32_t e){ asm volatile("fma.rn.bf16x2 pb7, %0, %1, %2;"::"r"(y),"r"(u),"r"(e)); }
template<> __device__ __forceinline__ void pb_cvt<7>(float lo, float hi){ asm volatile("cvt.rn.bf16x2.f32 pb7, %1, %0;"::"f"(lo),"f"(hi)); }
template<> __device__ __forceinline__ void pb_fma<8>(uint32_t y, uint32_t u, uint32_t e){ asm volatile("fma.rn.bf16x2 pb8, %0, %1, %2;"::"r"(y),"r"(u),"r"(e)); }
template<> __device__ __forceinline__ void pb_cvt<8>(float lo, float hi){ asm volatile("cvt.rn.bf16x2.f32 pb8, %1, %0;"::"f"(lo),"f"(hi)); }
template<> __device__ __forceinline__ void pb_fma<9>(uint32_t y, uint32_t u, uint32_t e){ asm volatile("fma.rn.bf16x2 pb9, %0, %1, %2;"::"r"(y),"r"(u),"r"(e)); }
template<> __device__ __forceinline__ void pb_cvt<9>(float lo, float hi){ asm volatile("cvt.rn.bf16x2.f32 pb9, %1, %0;"::"f"(lo),"f"(hi)); }
template<> __device__ __forceinline__ void pb_fma<10>(uint32_t y, uint32_t u, uint32_t e){ asm volatile("fma.rn.bf16x2 pb10, %0, %1, %2;"::"r"(y),"r"(u),"r"(e)); }
template<> __device__ __forceinline__ void pb_cvt<10>(float lo, float hi){ asm volatile("cvt.rn.bf16x2.f32 pb10, %1, %0;"::"f"(lo),"f"(hi)); }
template<> __device__ __forceinline__ void pb_fma<11>(uint32_t y, uint32_t u, uint32_t e){ asm volatile("fma.rn.bf16x2 pb11, %0, %1, %2;"::"r"(y),"r"(u),"r"(e)); }
template<> __device__ __forceinline__ void pb_cvt<11>(float lo, float hi){ asm volatile("cvt.rn.bf16x2.f32 pb11, %1, %0;"::"f"(lo),"f"(hi)); }
template<> __device__ __forceinline__ void pb_fma<12>(uint32_t y, uint32_t u, uint32_t e){ asm volatile("fma.rn.bf16x2 pb12, %0, %1, %2;"::"r"(y),"r"(u),"r"(e)); }
template<> __device__ __forceinline__ void pb_cvt<12>(float lo, float hi){ asm volatile("cvt.rn.bf16x2.f32 pb12, %1, %0;"::"f"(lo),"f"(hi)); }
template<> __device__ __forceinline__ void pb_fma<13>(uint32_t y, uint32_t u, uint32_t e){ asm volatile("fma.rn.bf16x2 pb13, %0, %1, %2;"::"r"(y),"r"(u),"r"(e)); }
template<> __device__ __forceinline__ void pb_cvt<13>(float lo, float hi){ asm volatile("cvt.rn.bf16x2.f32 pb13, %1, %0;"::"f"(lo),"f"(hi)); }
template<> __device__ __forceinline__ void pb_fma<14>(uint32_t y, uint32_t u, uint32_t e){ asm volatile("fma.rn.bf16x2 pb14, %0, %1, %2;"::"r"(y),"r"(u),"r"(e)); }
template<> __device__ __forceinline__ void pb_cvt<14>(float lo, float hi){ asm volatile("cvt.rn.bf16x2.f32 pb14, %1, %0;"::"f"(lo),"f"(hi)); }
template<> __device__ __forceinline__ void pb_fma<15>(uint32_t y, uint32_t u, uint32_t e){ asm volatile("fma.rn.bf16x2 pb15, %0, %1, %2;"::"r"(y),"r"(u),"r"(e)); }
template<> __device__ __forceinline__ void pb_cvt<15>(float lo, float hi){ asm volatile("cvt.rn.bf16x2.f32 pb15, %1, %0;"::"f"(lo),"f"(hi)); }
#define PB_ZERO() asm volatile("mov.b32 pb0, 0; mov.b32 pb1, 0; mov.b32 pb2, 0; mov.b32 pb3, 0; mov.b32 pb4, 0; mov.b32 pb5, 0; mov.b32 pb6, 0; mov.b32 pb7, 0; mov.b32 pb8, 0; mov.b32 pb9, 0; mov.b32 pb10, 0; mov.b32 pb11, 0; mov.b32 pb12, 0; mov.b32 pb13, 0; mov.b32 pb14, 0; mov.b32 pb15, 0; ")

#define FENCE()  asm volatile("wgmma.fence.sync.aligned;":::"memory")
#define COMMIT() asm volatile("wgmma.commit_group.sync.aligned;":::"memory")
#define WAITG(n) asm volatile("wgmma.wait_group.sync.aligned %0;"::"n"(n):"memory")
#define DEVI __device__ __forceinline__

constexpr uint32_t SM_XT   = 0;
constexpr uint32_t SM_ONES = 131072;
constexpr uint32_t SM_BAR  = 131584;
constexpr uint32_t SM_EP   = 131936;
constexpr uint32_t SM_CSB  = 131952;
constexpr uint32_t SM_KMX  = 132080;
constexpr uint32_t SM_RING = 132096;
constexpr uint32_t SM_STAT = 230400;
constexpr uint32_t SM_CS   = 231424;
constexpr uint32_t SM_TOTAL= 232448;
constexpr int B_XF=0, B_WKV=8, B_EM=16, B_WQ=22, B_WO=26, B_RES=27, B_GD=28, B_STAT=29, B_WBQ=30, B_WBKV=31, B_KVF=32, B_KVS=37, B_QD=38, B_CS=39, B_F1=40, B_LD=41, B_NUM=42;

__device__ __align__(1024) unsigned char g_x[2048*512*2];
__device__ __align__(1024) unsigned char g_o[2048*512*2];
__device__ __align__(128) unsigned long long g_stat[2048*8];
__device__ __align__(128) float g_kvacc[2*8*1088];
__device__ __align__(1024) unsigned char g_KV[131072];
__device__ __align__(128) float g_cs[8*320];
__device__ __align__(128) unsigned g_csc[8*32];
__device__ __align__(128) unsigned g_kmax[32];
__device__ __align__(128) unsigned g_fx[128*32];
__device__ __align__(128) unsigned g_fo[128*32];
__device__ __align__(128) unsigned g_kvc[8*4*32];
__device__ __align__(128) unsigned g_kc[16*32];
__device__ __align__(128) unsigned g_epoch[32];

#define TS(k)
#define TSR(v)
#define TSW(k,v)
struct Maps { CUtensorMap x, wkv, wq, woa, wbq, wob; };

template<int N> DEVI void regfence(float (&a)[N]){
#pragma unroll
  for(int i=0;i<N;i++) asm volatile("":"+f"(a[i])::"memory");
}
template<int N> DEVI void regfence(uint32_t (&a)[N]){
#pragma unroll
  for(int i=0;i<N;i++) asm volatile("":"+r"(a[i])::"memory");
}
DEVI uint64_t mkd(uint32_t lo, uint32_t hi){ uint64_t d; asm("mov.b64 %0, {%1,%2};":"=l"(d):"r"(lo),"r"(hi)); return d; }
__host__ __device__ constexpr uint32_t dhi(uint32_t sbo, uint32_t swz){ return (sbo>>4) | (swz<<30); }
DEVI uint32_t dlo(uint32_t addr, uint32_t lbo){ return ((addr&0x3FFFF)>>4) | ((lbo>>4)<<16); }

DEVI void mbar_init(uint32_t b, uint32_t n){ asm volatile("mbarrier.init.shared::cta.b64 [%0], %1;"::"r"(b),"r"(n):"memory"); }
DEVI void mbar_arrive(uint32_t b){ asm volatile("mbarrier.arrive.shared::cta.b64 _, [%0];"::"r"(b):"memory"); }
DEVI void mbar_expect(uint32_t b, uint32_t bytes){ asm volatile("mbarrier.arrive.expect_tx.shared::cta.b64 _, [%0], %1;"::"r"(b),"r"(bytes):"memory"); }
DEVI void mbar_wait(uint32_t b, uint32_t par){
  uint32_t ok; int n=0;
  while(true){
    asm volatile("{.reg .pred p; mbarrier.try_wait.parity.shared::cta.b64 p, [%1], %2; selp.u32 %0,1,0,p;}":"=r"(ok):"r"(b),"r"(par):"memory");
    if(ok) break;
    if(++n > (1<<22)) asm volatile("trap;");
  }
}
DEVI void mbar_wait_u(uint32_t b, uint32_t par){
  uint32_t ok; int n=0;
  while(true){
    asm volatile("{.reg .pred p; mbarrier.try_wait.parity.shared::cta.b64 p, [%1], %2; selp.u32 %0,1,0,p;}":"=r"(ok):"r"(b),"r"(par):"memory");
    if(__all_sync(~0u,ok)) break;
    if(++n > (1<<22)) asm volatile("trap;");
  }
}
DEVI uint32_t chunk_mask(uint32_t b0, int c, int lane, uint32_t par){
  uint32_t ok;
  asm volatile("{.reg .pred p; mbarrier.test_wait.parity.shared::cta.b64 p, [%1], %2; selp.u32 %0,1,0,p;}":"=r"(ok):"r"(b0+8*((c+lane)&7)),"r"(par):"memory");
  return __ballot_sync(~0u,ok);
}
DEVI uint4 ld_rlx4(const void* p){ uint4 v; asm volatile("ld.relaxed.gpu.global.v4.u32 {%0,%1,%2,%3}, [%4];":"=r"(v.x),"=r"(v.y),"=r"(v.z),"=r"(v.w):"l"(p):"memory"); return v; }
DEVI void bar_sync(int id, int n){ asm volatile("bar.sync %0, %1;"::"r"(id),"r"(n):"memory"); }
DEVI void bar_arrive(int id, int n){ asm volatile("bar.arrive %0, %1;"::"r"(id),"r"(n):"memory"); }
DEVI void fence_async_smem(){ asm volatile("fence.proxy.async.shared::cta;":::"memory"); }
DEVI void tma2d(uint32_t dst, const CUtensorMap* m, int c0, int c1, uint32_t bar){
  asm volatile("cp.async.bulk.tensor.2d.shared::cluster.global.mbarrier::complete_tx::bytes [%0], [%1, {%3, %4}], [%2];"
    ::"r"(dst),"l"(m),"r"(bar),"r"(c0),"r"(c1):"memory");
}
DEVI void tma_wkv(uint32_t dst, const CUtensorMap* m, int c0, int c1, uint32_t bar){
  asm volatile("cp.async.bulk.tensor.3d.shared::cluster.global.mbarrier::complete_tx::bytes [%0], [%1, {%3, %4, %5}], [%2];"
    ::"r"(dst),"l"(m),"r"(bar),"r"(c0),"r"(c1),"r"(1):"memory");
}
DEVI void bulk_ld(uint32_t dst, const void* src, uint32_t bytes, uint32_t bar){
  asm volatile("cp.async.bulk.shared::cluster.global.mbarrier::complete_tx::bytes [%0], [%1], %2, [%3];"
    ::"r"(dst),"l"(src),"r"(bytes),"r"(bar):"memory");
}
DEVI void bulk_st(void* dst, uint32_t src, uint32_t bytes){
  asm volatile("cp.async.bulk.global.shared::cta.bulk_group [%0], [%1], %2;"::"l"(dst),"r"(src),"r"(bytes):"memory");
  asm volatile("cp.async.bulk.commit_group;":::"memory");
}
DEVI void bulk_wait(){ asm volatile("cp.async.bulk.wait_group 0;":::"memory"); }
DEVI void bulk_red_f32(void* dst, uint32_t src, uint32_t bytes){
  asm volatile("cp.reduce.async.bulk.global.shared::cta.bulk_group.add.f32 [%0], [%1], %2;"::"l"(dst),"r"(src),"r"(bytes):"memory");
  asm volatile("cp.async.bulk.commit_group;":::"memory");
}
DEVI void bulk_max_u64(void* dst, uint32_t src, uint32_t bytes){
  asm volatile("cp.reduce.async.bulk.global.shared::cta.bulk_group.max.u64 [%0], [%1], %2;"::"l"(dst),"r"(src),"r"(bytes):"memory");
  asm volatile("cp.async.bulk.commit_group;":::"memory");
}
DEVI void l2_prefetch(const void* p, uint32_t bytes){ asm volatile("cp.async.bulk.prefetch.L2.global [%0], %1;"::"l"(p),"r"(bytes):"memory"); }
DEVI void map_prefetch(const CUtensorMap* m){ asm volatile("prefetch.tensormap [%0];"::"l"(m):"memory"); }
DEVI unsigned ld_rlx(const unsigned* p){ unsigned v; asm volatile("ld.relaxed.gpu.global.u32 %0, [%1];":"=r"(v):"l"(p):"memory"); return v; }
DEVI void st_rlx(unsigned* p, unsigned v){ asm volatile("st.relaxed.gpu.global.u32 [%0], %1;"::"l"(p),"r"(v):"memory"); }
DEVI void red_rlx(unsigned* p, unsigned v){ asm volatile("red.relaxed.gpu.global.add.u32 [%0], %1;"::"l"(p),"r"(v):"memory"); }
DEVI uint2 ld_rec(const void* p){ uint2 v; asm volatile("{.reg .b64 t; ld.relaxed.gpu.global.b64 t, [%2]; mov.b64 {%0,%1}, t;}":"=r"(v.x),"=r"(v.y):"l"(p):"memory"); return v; }
DEVI void st_rec(void* p, float a, float b, unsigned tag){ asm volatile("{.reg .b64 t; mov.b64 t, {%1,%2}; st.relaxed.gpu.global.b64 [%0], t;}"::"l"(p),"r"(__float_as_uint(a)),"r"((__float_as_uint(b)&~255u)|tag):"memory"); }
DEVI unsigned stat_tag(unsigned seq){ return seq%255u+1u; }
DEVI void poll_rlx(const unsigned* p, unsigned tgt){
  int n=0;
  while((int)(ld_rlx(p)-tgt) < 0){ if(++n > (1<<21)) asm volatile("trap;"); }
}
DEVI void red4f(float* p, float x, float y, float z, float w){ asm volatile("red.relaxed.gpu.global.add.v4.f32 [%0], {%1,%2,%3,%4};"::"l"(p),"f"(x),"f"(y),"f"(z),"f"(w):"memory"); }
DEVI float4 lds4f(uint32_t a){ float4 v; asm volatile("ld.shared.v4.f32 {%0,%1,%2,%3}, [%4];":"=f"(v.x),"=f"(v.y),"=f"(v.z),"=f"(v.w):"r"(a):"memory"); return v; }
DEVI void sts4f(uint32_t a, float x, float y, float z, float w){ asm volatile("st.shared.v4.f32 [%0], {%1,%2,%3,%4};"::"r"(a),"f"(x),"f"(y),"f"(z),"f"(w):"memory"); }
DEVI uint32_t lds1u(uint32_t a){ uint32_t v; asm volatile("ld.shared.u32 %0, [%1];":"=r"(v):"r"(a):"memory"); return v; }
DEVI void sts1u(uint32_t a, uint32_t x){ asm volatile("st.shared.u32 [%0], %1;"::"r"(a),"r"(x):"memory"); }
DEVI uint4 ldg4(const void* p){ uint4 v; asm volatile("ld.global.nc.L1::no_allocate.v4.u32 {%0,%1,%2,%3}, [%4];":"=r"(v.x),"=r"(v.y),"=r"(v.z),"=r"(v.w):"l"(p)); return v; }
DEVI int fresh_tid(){ int v; asm volatile("mov.u32 %0, %%tid.x;":"=r"(v)); return v; }
DEVI uint32_t prmt(uint32_t a, uint32_t b, uint32_t sel){ uint32_t d; asm("prmt.b32 %0, %1, %2, %3;":"=r"(d):"r"(a),"r"(b),"r"(sel)); return d; }
DEVI uint32_t pack2u(uint32_t lo, uint32_t hi){ uint32_t p; asm("cvt.rn.bf16x2.f32 %0, %1, %2;":"=r"(p):"f"(__uint_as_float(hi)),"f"(__uint_as_float(lo))); return p; }
DEVI uint32_t pack2(float lo, float hi){ uint32_t p; asm("cvt.rn.bf16x2.f32 %0, %1, %2;":"=r"(p):"f"(hi),"f"(lo)); return p; }
DEVI float bflo(uint32_t p){ return __uint_as_float(p<<16); }
DEVI float bfhi(uint32_t p){ return __uint_as_float(p&0xffff0000u); }
DEVI float ex2(float x){ float y; asm("ex2.approx.ftz.f32 %0, %1;":"=f"(y):"f"(x)); return y; }
constexpr float PHC=1.000001f;
DEVI float phi(float a, float rs, float cs, float nrm){
  const float t1=fmaf(a,rs,fmaf(cs,nrm,PHC));
  const float e=ex2(fmaf(t1,1.4426950408889634f,-PHC*1.4426950408889634f))+1e-6f;
  return t1>PHC ? t1 : e;
}
DEVI float rcpf(float x){ float r; asm("rcp.approx.f32 %0, %1;":"=f"(r):"f"(x)); return r; }
DEVI void red_rel(unsigned* p, unsigned v){ asm volatile("red.release.gpu.global.add.u32 [%0], %1;"::"l"(p),"r"(v):"memory"); }
DEVI void stsm4(uint32_t a, uint32_t r0, uint32_t r1, uint32_t r2, uint32_t r3){
  asm volatile("stmatrix.sync.aligned.m8n8.x4.shared.b16 [%0], {%1,%2,%3,%4};"::"r"(a),"r"(r0),"r"(r1),"r"(r2),"r"(r3):"memory");
}
DEVI void ldsm4(uint32_t a, uint32_t& r0, uint32_t& r1, uint32_t& r2, uint32_t& r3){
  asm volatile("ldmatrix.sync.aligned.m8n8.x4.shared.b16 {%0,%1,%2,%3}, [%4];":"=r"(r0),"=r"(r1),"=r"(r2),"=r"(r3):"r"(a):"memory");
}
DEVI void ldsm4t(uint32_t a, uint32_t& r0, uint32_t& r1, uint32_t& r2, uint32_t& r3){
  asm volatile("ldmatrix.sync.aligned.m8n8.x4.trans.shared.b16 {%0,%1,%2,%3}, [%4];":"=r"(r0),"=r"(r1),"=r"(r2),"=r"(r3):"r"(a):"memory");
}
DEVI void mma16816(float (&c)[4], uint32_t a0, uint32_t a1, uint32_t a2, uint32_t a3, uint32_t b0, uint32_t b1){
  asm volatile("mma.sync.aligned.m16n8k16.row.col.f32.bf16.bf16.f32 {%0,%1,%2,%3}, {%4,%5,%6,%7}, {%8,%9}, {%0,%1,%2,%3};"
    :"+f"(c[0]),"+f"(c[1]),"+f"(c[2]),"+f"(c[3]):"r"(a0),"r"(a1),"r"(a2),"r"(a3),"r"(b0),"r"(b1));
}
DEVI uint32_t movm(uint32_t a){ uint32_t d; asm volatile("movmatrix.sync.aligned.m8n8.trans.b16 %0, %1;":"=r"(d):"r"(a)); return d; }
DEVI float2 lds2(uint32_t a){ float2 v; asm volatile("ld.shared.v2.f32 {%0,%1}, [%2];":"=f"(v.x),"=f"(v.y):"r"(a):"memory"); return v; }
DEVI float lds1(uint32_t a){ float v; asm volatile("ld.shared.f32 %0, [%1];":"=f"(v):"r"(a):"memory"); return v; }
DEVI uint4 lds4u(uint32_t a){ uint4 v; asm volatile("ld.shared.v4.u32 {%0,%1,%2,%3}, [%4];":"=r"(v.x),"=r"(v.y),"=r"(v.z),"=r"(v.w):"r"(a):"memory"); return v; }
DEVI uint2 lds2u(uint32_t a){ uint2 v; asm volatile("ld.shared.v2.u32 {%0,%1}, [%2];":"=r"(v.x),"=r"(v.y):"r"(a):"memory"); return v; }
DEVI void sts4u(uint32_t a, uint32_t x, uint32_t y, uint32_t z, uint32_t w){ asm volatile("st.shared.v4.u32 [%0], {%1,%2,%3,%4};"::"r"(a),"r"(x),"r"(y),"r"(z),"r"(w):"memory"); }
DEVI void sts2u(uint32_t a, uint32_t x, uint32_t y){ asm volatile("st.shared.v2.u32 [%0], {%1,%2};"::"r"(a),"r"(x),"r"(y):"memory"); }
DEVI void sts2(uint32_t a, float x, float y){ asm volatile("st.shared.v2.f32 [%0], {%1,%2};"::"r"(a),"f"(x),"f"(y):"memory"); }
DEVI void sts1(uint32_t a, float x){ asm volatile("st.shared.f32 [%0], %1;"::"r"(a),"f"(x):"memory"); }
DEVI bool wg_all(int id, bool p){
  uint32_t o;
  asm volatile("{.reg .pred p,q; setp.ne.u32 p, %1, 0; barrier.red.and.pred q, %2, 128, p; selp.u32 %0,1,0,q;}":"=r"(o):"r"((uint32_t)p),"r"(id):"memory");
  return __all_sync(~0u,o!=0);
}

constexpr float MAGIC_P = 415.5f + 0.00390625f;
constexpr float MAGIC_M = 415.5f - 447.f + 1.5849625007f + 0.001f;
constexpr float BOUND   = 94.f;
constexpr float MAGIC_P2 = 376.f + 0.00390625f;
constexpr float MAGIC_M2 = 376.f - 384.f + 1.5849625007f + 0.001f;
constexpr float BOUND2   = 118.f;
template<bool WIDE> DEVI uint32_t exp_poly(float t0, float t1, uint32_t cm1, uint32_t cu){
  uint32_t y,u,e,p;
  asm("prmt.b32 %0, %1, %2, 0x6521;":"=r"(y):"r"(__float_as_uint(t0)),"r"(__float_as_uint(t1)));
  asm("lop3.b32 %0, %1, 0x007F007F, %2, 0xEA;":"=r"(u):"r"(y),"r"(cu));
  if(WIDE) e=y&0x7f807f80u;
  else asm("mad.lo.u32 %0, %1, %2, %3;":"=r"(e):"r"(u),"r"(cm1),"r"(y));
  asm("fma.rn.bf16x2 %0, %1, %2, %3;":"=r"(p):"r"(y),"r"(u),"r"(e));
  return p;
}
constexpr int NMUFU=4;
__host__ __device__ constexpr bool is_mufu(int i){ return ((i+1)*NMUFU)/16 != (i*NMUFU)/16; }
template<bool WIDE> DEVI void exp_block(const float (&s)[32], uint32_t (&p)[16], uint32_t cm1, uint32_t cu){
#pragma unroll
  for(int i=0;i<16;i++){
    if(is_mufu(i)) p[i]=pack2(ex2(s[2*i]), ex2(s[2*i+1]));
    else p[i]=exp_poly<WIDE>(s[2*i], s[2*i+1], cm1, cu);
  }
}

template<bool WIDE, int I> DEVI void exp_pb(const float (&s)[32], uint32_t cm1, uint32_t cu){
  if(is_mufu(I)) pb_cvt<I>(ex2(s[2*I]), ex2(s[2*I+1]));
  else {
    uint32_t y,u,e;
    asm("prmt.b32 %0, %1, %2, 0x6521;":"=r"(y):"r"(__float_as_uint(s[2*I])),"r"(__float_as_uint(s[2*I+1])));
    asm("lop3.b32 %0, %1, 0x007F007F, %2, 0xEA;":"=r"(u):"r"(y),"r"(cu));
    if(WIDE) e=y&0x7f807f80u;
    else asm("mad.lo.u32 %0, %1, %2, %3;":"=r"(e):"r"(u),"r"(cm1),"r"(y));
    pb_fma<I>(y,u,e);
  }
  if constexpr (I<15) exp_pb<WIDE,I+1>(s,cm1,cu);
}
#define PV_PB(dv) do{ wgmma_pv_pb0(o,mkd((dv),khi),1); wgmma_pv_pb1(o,mkd((dv)+VS,khi),1); wgmma_pv_pb2(o,mkd((dv)+2*VS,khi),1); wgmma_pv_pb3(o,mkd((dv)+3*VS,khi),1); }while(0)
constexpr uint32_t VS=32u-(32u<<16);
template<bool WIDE> DEVI bool att_tile(uint32_t q0, uint32_t q1, uint32_t q2, uint32_t q3, uint32_t qa, int bid, uint32_t kd0, uint32_t vd0, uint32_t bkv, uint32_t it, uint32_t cm1, uint32_t cu){
  constexpr uint32_t khi=dhi(256,3);
  float s[32], o[12];
  uint32_t pA[16];
  uint32_t dk=kd0, dv=vd0, wb=8; int wds=1;
#pragma unroll
  for(int i=0;i<12;i++) o[i]=0.f;
#pragma unroll 1
  for(int hf=0;hf<2;hf++){
#pragma unroll
    for(int i=0;i<32;i++) s[i]= is_mufu(i>>1)? (WIDE? MAGIC_M2 : MAGIC_M) : (WIDE? MAGIC_P2 : MAGIC_P);
    regfence(s); regfence(o);
    FENCE();
    wgmma_rs_n64(s,q0,q1,q2,q3,mkd(dk,khi),1); COMMIT();
    WAITG(0); regfence(s);
    exp_block<WIDE>(s,pA,cm1,cu);
#pragma unroll 1
    for(int ds=0;ds<7;ds++){
      if(ds==wds){ mbar_wait_u(bkv+wb,it); wb+=8; wds= wds==1? 4 : 0; }
      regfence(pA);
      FENCE();
      wgmma_rs_n64(s,q0,q1,q2,q3,mkd(dk+128,khi),1); COMMIT();
#pragma unroll
      for(int u=0;u<4;u++) wgmma_rs_n24_tb(o,pA[4*u],pA[4*u+1],pA[4*u+2],pA[4*u+3],mkd(dv+u*VS,khi),1);
      COMMIT();
      WAITG(1); regfence(s);
      exp_pb<WIDE,0>(s,cm1,cu);
      FENCE();
      wgmma_rs_n64(s,q0,q1,q2,q3,mkd(dk+256,khi),1); COMMIT();
      PV_PB(dv+4*VS);
      COMMIT();
      WAITG(WIDE? 0 : 1); regfence(s);
      exp_block<WIDE>(s,pA,cm1,cu);
      dk+=256; dv+=8*VS;
    }
    regfence(pA);
    FENCE();
    wgmma_rs_n64(s,q0,q1,q2,q3,mkd(dk+128,khi),1); COMMIT();
#pragma unroll
    for(int u=0;u<4;u++) wgmma_rs_n24_tb(o,pA[4*u],pA[4*u+1],pA[4*u+2],pA[4*u+3],mkd(dv+u*VS,khi),1);
    COMMIT();
    WAITG(1); regfence(s);
    exp_pb<WIDE,0>(s,cm1,cu);
    FENCE();
    PV_PB(dv+4*VS);
    COMMIT();
    WAITG(0); regfence(o);
    dk+=256; dv+=8*VS;
  }
  const float TINY=8.0779356694631609e-28f;
  float big=fmaxf(o[8],o[10]);
#pragma unroll
  for(int i=0;i<8;i++) big+=fabsf(o[i]);
  const bool ok=wg_all(bid,(o[8]>=TINY) && (o[10]>=TINY) && (big<=3.0e38f));
  if(ok){
    const float i0=1.f/o[8], i1=1.f/o[10];
    stsm4(qa,pack2(o[0]*i0,o[1]*i0),pack2(o[2]*i1,o[3]*i1),pack2(o[4]*i0,o[5]*i0),pack2(o[6]*i1,o[7]*i1));
  }
  return ok;
}

DEVI void slow_tile(uint32_t qa, int bid, uint32_t kd0, uint32_t vd0, uint32_t bkv, uint32_t it, bool wide){
  constexpr uint32_t khi=dhi(256,3);
  uint32_t f0r,f1r,f2r,f3r;
  ldsm4(qa,f0r,f1r,f2r,f3r);
  bool ok=wg_all(bid,wide);
  if(ok) ok=att_tile<true>(f0r,f1r,f2r,f3r,qa,bid,kd0,vd0,bkv,it,0u,0xbf00bf00u);
  if(!ok){
    for(int p=1;p<4;p++) mbar_wait(bkv+8*p,it);
    float m0=-INFINITY, m1=-INFINITY;
    float s2[32], o2[12]; uint32_t p2[16];
#pragma unroll
    for(int i=0;i<12;i++) o2[i]=0.f;
#pragma unroll
    for(int i=0;i<32;i++) s2[i]=0.f;
    uint32_t ek=kd0, ev=vd0;
#pragma unroll 1
    for(int j=0;j<32;j++){
      regfence(s2);
      FENCE();
      wgmma_rs_n64(s2,f0r,f1r,f2r,f3r,mkd(ek,khi),j&15); COMMIT();
      WAITG(0); regfence(s2);
      float x0=m0,x1=m1;
#pragma unroll
      for(int i=0;i<8;i++){ x0=fmaxf(x0,fmaxf(s2[4*i],s2[4*i+1])); x1=fmaxf(x1,fmaxf(s2[4*i+2],s2[4*i+3])); }
      x0=fmaxf(x0,__shfl_xor_sync(~0u,x0,1)); x0=fmaxf(x0,__shfl_xor_sync(~0u,x0,2));
      x1=fmaxf(x1,__shfl_xor_sync(~0u,x1,1)); x1=fmaxf(x1,__shfl_xor_sync(~0u,x1,2));
      const float f0=ex2(m0-x0), f1=ex2(m1-x1); m0=x0; m1=x1;
#pragma unroll
      for(int i=0;i<3;i++){ o2[4*i]*=f0; o2[4*i+1]*=f0; o2[4*i+2]*=f1; o2[4*i+3]*=f1; }
#pragma unroll
      for(int i=0;i<8;i++){ p2[2*i]=pack2(ex2(s2[4*i]-m0),ex2(s2[4*i+1]-m0)); p2[2*i+1]=pack2(ex2(s2[4*i+2]-m1),ex2(s2[4*i+3]-m1)); }
      regfence(p2); regfence(o2);
      FENCE();
#pragma unroll
      for(int u=0;u<4;u++) wgmma_rs_n24_tb(o2,p2[4*u],p2[4*u+1],p2[4*u+2],p2[4*u+3],mkd(ev+u*VS,khi),1);
      COMMIT();
      WAITG(0); regfence(o2);
      ek+=128; ev+=4*VS;
    }
    const float i0=1.f/o2[8], i1=1.f/o2[10];
    __syncwarp();
    stsm4(qa,pack2(o2[0]*i0,o2[1]*i0),pack2(o2[2]*i1,o2[3]*i1),pack2(o2[4]*i0,o2[5]*i0),pack2(o2[6]*i1,o2[7]*i1));
  }
}

DEVI void row_stats(uint32_t sb, int r, int row, unsigned tag){
  const unsigned long long* sp=g_stat+(size_t)(r*1024+row);
  uint2 a[8]; int n=0;
  while(true){
#pragma unroll
    for(int j=0;j<8;j++) a[j]=ld_rec(sp+j*128);
    unsigned bad=0;
#pragma unroll
    for(int j=0;j<8;j++) bad|=a[j].y^tag;
    if(!(bad&255u)) break;
    if(++n>(1<<21)) asm volatile("trap;");
  }
  float s=0, m2=0;
#pragma unroll
  for(int j=0;j<8;j++){ s+=__uint_as_float(a[j].x); m2+=__uint_as_float(a[j].y&~255u); }
  const float mean=s*(1.f/512); float dd=0;
#pragma unroll
  for(int j=0;j<8;j++){ float d=__uint_as_float(a[j].x)*(1.f/64)-mean; dd+=d*d; }
  m2+=64.f*dd;
  const float rstd=1.f/sqrtf(m2*(1.f/512)+1e-5f);
  sts2(sb+SM_STAT+row*8, rstd, mean*rstd);
  mbar_arrive(sb+SM_BAR+8*B_STAT);
  __syncwarp();
}
DEVI void acc8(float (&s)[8], const uint4& v){
  s[0]+=bflo(v.x); s[1]+=bfhi(v.x); s[2]+=bflo(v.y); s[3]+=bfhi(v.y); s[4]+=bflo(v.z); s[5]+=bfhi(v.z); s[6]+=bflo(v.w); s[7]+=bfhi(v.w);
}

__global__ void __launch_bounds__(512,1)
fused_kernel(const __grid_constant__ Maps maps, const unsigned char* __restrict__ wqkv, const unsigned char* __restrict__ woa,
             const unsigned char* __restrict__ wbq, const unsigned char* __restrict__ wbk, const unsigned char* __restrict__ wbv,
             const unsigned char* __restrict__ wob, __nv_bfloat16* __restrict__ out, uint32_t cm1, uint32_t cu)
{
  extern __shared__ __align__(1024) unsigned char smem_raw[];
  asm volatile(".reg .b32 pb<16>;");
  const uint32_t sb = (uint32_t)__cvta_generic_to_shared(smem_raw);
  const int bid=blockIdx.x, r=bid>>3, c=bid&7;
  #define BAR(i) (sb+SM_BAR+8*(i))
  #define SLOT(i) (sb+SM_RING+16384*(i))
  #define WSLOT(i) SLOT((i)<2? (i)^1 : (i)<6? (i) : (i)^7)
  #define IDS() const int tid=fresh_tid(), lane=tid&31; const int warp=__shfl_sync(0xffffffffu, tid>>5, 0), wg=warp>>2, w4=warp&3; \
    const int g=lane>>2, t=lane&3; const uint32_t mrow=(uint32_t)(((wg&1)*64 + w4*16 + (lane&7) + ((lane>>3)&1)*8) * 128), mx7=lane&7, mhi=lane>>4; \
    (void)g; (void)t; (void)mrow; (void)mx7; (void)mhi; (void)wg; (void)w4
  #define TILE_ADDR(base,h) ((base) + mrow + (((2*(h)+mhi) ^ mx7)<<4))
  #define EPOCH() lds1u(sb+SM_EP)

  {
    IDS();
    if(warp<2){
      if(lane==0){
        const uint32_t b= warp==0? BAR(B_XF) : BAR(B_WKV);
#pragma unroll
        for(int i=0;i<8;i++) mbar_init(b+8*i,1);
        asm volatile("fence.mbarrier_init.release.cluster;":::"memory");
        fence_async_smem();
        if(warp==0){
#pragma unroll 1
          for(int i=0;i<8;i++){ const int kc=(c+i)&7; mbar_expect(b+8*kc,16384); tma2d(sb+SM_XT+kc*16384,&maps.x,kc*64,r*128,b+8*kc); }
        } else {
#pragma unroll 1
          for(int i=0;i<6;i++){ mbar_expect(b+8*i,16384); tma_wkv(WSLOT(i),&maps.wkv,c*64,((c+i)&7)*64,b+8*i); }
        }
      }
    } else if(warp==8){
      const int i=B_EM+lane;
      if(sb&1023) asm volatile("trap;");
      if(i<B_NUM){
        mbar_init(BAR(i), i<B_EM+6? 8 : i==B_F1? 3 : i==B_LD? 4 : (i==B_WBKV || i==B_QD || i==B_GD)? 2 : (i==B_STAT || i==B_KVS)? 128 : 1);
        asm volatile("fence.mbarrier_init.release.cluster;":::"memory");
        fence_async_smem();
      }
    } else if(warp==9){
      sts4u(sb+SM_ONES+lane*16,0x3f803f80u,0x3f803f80u,0x3f803f80u,0x3f803f80u); fence_async_smem();
    } else if(warp==10){
      if(lane==0) sts1u(sb+SM_EP,*(volatile unsigned*)g_epoch);
    }
    uint4 v[8], u0=make_uint4(0,0,0,0), u1=u0;
    if(wg==3){
      const unsigned char* p= w4<3? wqkv+(size_t)(r*32+(lane>>3))*3072+w4*1024 : wbq+(size_t)(r*32+(lane>>3))*1024;
      const uint32_t rs= w4<3? 4*3072u : 4*1024u;
      p+=c*128+(lane&7)*16;
#pragma unroll
      for(int i=0;i<8;i++) v[i]=ldg4(p+i*rs);
      if(w4<2){ const unsigned char* q=(w4==0? wbk : wbv)+r*1024+lane*16; u0=ldg4(q); u1=ldg4(q+512); }
    }
    __syncthreads();
    if(wg==3){
      float s[8]={0,0,0,0,0,0,0,0};
#pragma unroll
      for(int i=0;i<8;i++) acc8(s,v[i]);
#pragma unroll
      for(int i=0;i<8;i++){ s[i]+=__shfl_xor_sync(~0u,s[i],8); s[i]+=__shfl_xor_sync(~0u,s[i],16); }
      if(lane<8){ sts4f(sb+SM_CS+w4*256+lane*32,s[0],s[1],s[2],s[3]); sts4f(sb+SM_CS+w4*256+lane*32+16,s[4],s[5],s[6],s[7]); }
      if(w4<2){
#pragma unroll
        for(int i=0;i<8;i++) s[i]=0.f;
        acc8(s,u0); acc8(s,u1);
#pragma unroll
        for(int i=0;i<8;i++){ s[i]+=__shfl_xor_sync(~0u,s[i],2); s[i]+=__shfl_xor_sync(~0u,s[i],4); s[i]+=__shfl_xor_sync(~0u,s[i],8); s[i]+=__shfl_xor_sync(~0u,s[i],16); }
        if(lane<2){ sts4f(sb+SM_CSB+w4*64+lane*32,s[0],s[1],s[2],s[3]); sts4f(sb+SM_CSB+w4*64+lane*32+16,s[4],s[5],s[6],s[7]); }
      }
      fence_async_smem();
      bar_arrive(15,160);
    }
    { const int l=0; (void)l; TS(9); }
  }

#pragma unroll 1
  for(int l=0;l<4;l++){
    const int it=l>>1; const uint32_t lp=l&1;
    {
    IDS();
    if(lp==0){
      if(wg<2){
        float acc[64];
#pragma unroll
        for(int i=0;i<64;i++) acc[i]=0.f;
        regfence(acc);
#pragma unroll 1
        for(int i=0;i<8;i++){
          const int kc=(c+i)&7;
          mbar_wait_u(BAR(B_XF+kc),0);
          if(i==0) TS(10);
          mbar_wait_u(BAR(B_WKV+i),it);
          if(i==0) TS(11); if(i==3) TS(12); if(i==6) TS(13);
          const uint32_t sl=WSLOT(i);
          const uint32_t da=dlo(sb+SM_XT+kc*16384+wg*8192,16), db=dlo(sl,8192);
          FENCE();
#pragma unroll
          for(int kk=0;kk<4;kk++) wgmma_ss_n128_tb(acc,mkd(da+kk*2,dhi(1024,1)),mkd(db+kk*128,dhi(1024,1)),1);
          COMMIT();
          if(i>0){ WAITG(1); if(i<7 && lane==0) mbar_arrive(BAR(B_EM+i-1)); }
        }
        WAITG(0); regfence(acc);
        TS(1);
        bar_sync(1,256);
        mbar_wait(BAR(B_CS),0);
        mbar_wait(BAR(B_STAT),lp);
        {
          const int row=wg*64+w4*16+g;
          const float2 s0=lds2(sb+SM_STAT+row*8), s1=lds2(sb+SM_STAT+row*8+64);
          float2 cs[16];
#pragma unroll
          for(int j=0;j<16;j++) cs[j]=lds2(sb+SM_CS+(64+8*j+2*t)*4);
          uint32_t p[32];
#pragma unroll
          for(int j=0;j<8;j++){
            const float* a=&acc[4*j]; const float* b=&acc[32+4*j];
            p[2*j]   =pack2(phi(a[0],s0.x,cs[j].x,-s0.y),phi(a[1],s0.x,cs[j].y,-s0.y));
            p[2*j+1] =pack2(phi(a[2],s1.x,cs[j].x,-s1.y),phi(a[3],s1.x,cs[j].y,-s1.y));
            p[16+2*j]=pack2(b[0]*s0.x-cs[8+j].x*s0.y,b[1]*s0.x-cs[8+j].y*s0.y);
            p[17+2*j]=pack2(b[2]*s1.x-cs[8+j].x*s1.y,b[3]*s1.x-cs[8+j].y*s1.y);
          }
#pragma unroll
          for(int h=0;h<4;h++){
            stsm4(TILE_ADDR(SLOT(0),h),p[4*h],p[4*h+1],p[4*h+2],p[4*h+3]);
            stsm4(TILE_ADDR(SLOT(1),h),p[16+4*h],p[17+4*h],p[18+4*h],p[19+4*h]);
          }
        }
        TSR(te);
        bar_sync(4+3*wg,128);
        {
          float c0[4]={0,0,0,0},c1[4]={0,0,0,0},z0[4]={0,0,0,0},z1[4]={0,0,0,0};
          const uint32_t off=(uint32_t)(wg*8192+((lane&7)+(lane>>4)*8)*128) + (((2*w4+((lane>>3)&1))^(lane&7))<<4);
          uint32_t k[16], v[16];
#pragma unroll
          for(int ks=0;ks<4;ks++){
            ldsm4t(SLOT(0)+ks*2048+off,k[4*ks],k[4*ks+1],k[4*ks+2],k[4*ks+3]);
            ldsm4t(SLOT(1)+ks*2048+off,v[4*ks],v[4*ks+1],v[4*ks+2],v[4*ks+3]);
          }
#pragma unroll
          for(int ks=0;ks<4;ks++){
            mma16816(c0,v[4*ks],v[4*ks+1],v[4*ks+2],v[4*ks+3],k[4*ks],k[4*ks+2]); mma16816(c1,v[4*ks],v[4*ks+1],v[4*ks+2],v[4*ks+3],k[4*ks+1],k[4*ks+3]);
            mma16816(z0,0x3f803f80u,0x3f803f80u,0x3f803f80u,0x3f803f80u,k[4*ks],k[4*ks+2]);
            mma16816(z1,0x3f803f80u,0x3f803f80u,0x3f803f80u,0x3f803f80u,k[4*ks+1],k[4*ks+3]);
          }
          const float* ga=g_kvacc+(it*8+c)*1088+w4*272+lane*4;
          bar_sync(4+3*wg,128);
          const uint32_t sp=SLOT(0)+wg*24576+2304+w4*1088;
          sts4f(sp+lane*16,c0[0],c0[1],c1[0],c1[1]); sts4f(sp+512+lane*16,c0[2],c0[3],c1[2],c1[3]);
          if(lane<4) sts4f(sp+1024+lane*16,z0[0],z0[1],z1[0],z1[1]);
          fence_async_smem(); __syncwarp();
          bar_arrive(3,512);
          unsigned* cnt=g_kvc+(c*4+w4)*32;
          if(lane==0){ bulk_red_f32((void*)ga, sp, 1088); bulk_wait(); red_rlx(cnt,1); }
          TS(3); TSW(2,te);
          if(wg==0){
            if(lane==0) poll_rlx(cnt,(EPOCH()*2+it+1)*32);
            __syncwarp();
            TS(4);
            const uint4 a=ld_rlx4(ga), b=ld_rlx4(ga+128), z=ld_rlx4(ga+256-(lane&~3)*4);
            const uint32_t st=SLOT(0)+w4*544;
            sts4u(st+lane*16,pack2u(a.x,a.y),pack2u(a.z,a.w),pack2u(b.x,b.y),pack2u(b.z,b.w));
            if(lane<4) sts2u(st+512+lane*8,pack2u(z.x,z.y),pack2u(z.z,z.w));
            mbar_arrive(BAR(B_KVS));
          } else if(tid==160){
            mbar_expect(BAR(B_WO),65536);
            for(int p=0;p<4;p++){ mbar_wait(BAR(B_EM+p),1); tma2d(SLOT(2+p),&maps.woa,c*64,p*128,BAR(B_WO)); }
          }
          __syncwarp();
        }
      } else {
        if(wg==3){
          const int row=tid-384;
          const unsigned tag=stat_tag(EPOCH()*4+l);
          if(l==0){
            mbar_wait(BAR(B_XF+c),0);
            uint32_t v[32];
#pragma unroll
            for(int j=0;j<8;j++){ uint4 a=lds4u(sb+SM_XT+c*16384+row*128+((j^(row&7))<<4)); v[4*j]=a.x; v[4*j+1]=a.y; v[4*j+2]=a.z; v[4*j+3]=a.w; }
            float s0=0,s1=0;
#pragma unroll
            for(int j=0;j<32;j++){ s0+=bflo(v[j]); s1+=bfhi(v[j]); }
            const float m=(s0+s1)*(1.f/64); float q0=0,q1=0;
#pragma unroll
            for(int j=0;j<32;j++){ float d0=bflo(v[j])-m, d1=bfhi(v[j])-m; q0+=d0*d0; q1+=d1*d1; }
            st_rec(g_stat+bid*128+row,s0+s1,q0+q1,tag);
          } else { mbar_wait(BAR(B_GD),1); mbar_wait(BAR(B_XF+c),0); }
          row_stats(sb,r,row,tag);
          TS(0);
        } else if(warp==10){
          if(l==0){
            mbar_wait(BAR(B_WKV),0);
            if(lane<2) l2_prefetch((lane==0? woa : wob)+bid*4096,4096);
            else if(lane<6) map_prefetch(&maps.wq+(lane-2));
          }
          if(lane==0){
            for(int i=0;i<6;i++){
              mbar_wait(BAR(B_EM+i),i<4? 0:it);
              if(i<2){ mbar_expect(BAR(B_WKV+6+i),16384); tma_wkv(WSLOT(6+i),&maps.wkv,c*64,((c+6+i)&7)*64,BAR(B_WKV+6+i)); }
              else { mbar_expect(BAR(B_WQ+i-2),16384); tma2d(SLOT(i),&maps.wq,c*64,(i-2)*128,BAR(B_WQ+i-2)); }
            }
          }
          __syncwarp();
        } else if(warp==11 && l==0){
          bar_sync(15,160);
          if(lane==0){
            mbar_expect(BAR(B_CS),1152);
            bulk_red_f32(g_cs+c*320,sb+SM_CS,1024); bulk_red_f32(g_cs+c*320+256,sb+SM_CSB,128); bulk_wait();
            red_rlx(g_csc+c*32,1);
            poll_rlx(g_csc+c*32,(EPOCH()+1)*16);
            bulk_ld(sb+SM_CS,g_cs+c*320,1024,BAR(B_CS)); bulk_ld(sb+SM_CSB,g_cs+c*320+256,128,BAR(B_CS));
          }
          __syncwarp();
          TS(4);
        }
        mbar_wait(BAR(B_WQ+(lane&3)),it);
        __syncwarp();
        float acc[32];
#pragma unroll
        for(int i=0;i<32;i++) acc[i]=0.f;
        regfence(acc);
        bar_sync(3,512);
#pragma unroll 1
        for(int kc=0;kc<8;kc++){
          const uint32_t da=dlo(sb+SM_XT+kc*16384+(wg&1)*8192,16), db=dlo(SLOT(2)+kc*8192,8192);
          FENCE();
#pragma unroll
          for(int kk=0;kk<4;kk++) wgmma_ss_n64_tb(acc,mkd(da+kk*2,dhi(1024,1)),mkd(db+kk*128,dhi(1024,1)),1);
          COMMIT();
          if(kc>0 && !(kc&1)){ WAITG(1); if(lane==0) mbar_arrive(BAR(B_EM+(kc>>1)-1)); }
        }
        WAITG(0); regfence(acc);
        if(lane==0) mbar_arrive(BAR(B_EM+3));
        TS(1);
        mbar_wait(BAR(B_CS),0);
        mbar_wait(BAR(B_STAT),lp);
        uint32_t aq[16];
        {
          const int row=(wg&1)*64+w4*16+g;
          const float2 s0=lds2(sb+SM_STAT+row*8), s1=lds2(sb+SM_STAT+row*8+64);
#pragma unroll
          for(int j=0;j<8;j++){
            float2 cs=lds2(sb+SM_CS+(8*j+2*t)*4);
            const float* a=&acc[4*j];
            aq[2*j]  =pack2(phi(a[0],s0.x,cs.x,-s0.y),phi(a[1],s0.x,cs.y,-s0.y));
            aq[2*j+1]=pack2(phi(a[2],s1.x,cs.x,-s1.y),phi(a[3],s1.x,cs.y,-s1.y));
          }
        }
        TS(2);
        mbar_wait(BAR(B_KVS),it);
        __syncwarp();
        TSR(tk);
        {
          uint4 a[4]; uint2 z[4]; float n0[4][4],n1[4][4],dn[4][4];
#pragma unroll
          for(int h=0;h<4;h++){ const uint32_t st=SLOT(0)+h*544; a[h]=lds4u(st+lane*16); z[h]=lds2u(st+512+t*8); }
#pragma unroll
          for(int h=0;h<4;h++){
#pragma unroll
            for(int i=0;i<4;i++){ n0[h][i]=0.f; n1[h][i]=0.f; dn[h][i]=0.f; }
            mma16816(dn[h],aq[4*h],aq[4*h+1],aq[4*h+2],aq[4*h+3],z[h].x,z[h].y);
            mma16816(n0[h],aq[4*h],aq[4*h+1],aq[4*h+2],aq[4*h+3],a[h].x,a[h].y);
            mma16816(n1[h],aq[4*h],aq[4*h+1],aq[4*h+2],aq[4*h+3],a[h].z,a[h].w);
          }
#pragma unroll
          for(int h=0;h<4;h++){
            const float i0=rcpf(dn[h][0]+1e-6f), i1=rcpf(dn[h][2]+1e-6f);
            stsm4(TILE_ADDR(SLOT(1),h),pack2(n0[h][0]*i0,n0[h][1]*i0),pack2(n0[h][2]*i1,n0[h][3]*i1),pack2(n1[h][0]*i0,n1[h][1]*i0),pack2(n1[h][2]*i1,n1[h][3]*i1));
          }
        }
        TSR(t1);
        fence_async_smem();
        TSR(t2);
        bar_sync(2,256);
        TS(5); TSW(4,tk); TSW(10,t1); TSW(11,t2);
      }
    } else {
      if(wg<2){
        float acc[32];
#pragma unroll
        for(int i=0;i<32;i++) acc[i]=0.f;
        regfence(acc);
        if(wg==0){ row_stats(sb,r,tid,stat_tag(EPOCH()*4+l)); TS(0); }
        mbar_wait_u(BAR(B_WBQ),it);
        bar_sync(13,352);
        uint32_t rdy=chunk_mask(BAR(B_XF),c,lane,0);
#pragma unroll 1
        for(int i=0;i<8;i++){
          const int kc=(c+i)&7;
          if(!((rdy>>i)&1)){ mbar_wait_u(BAR(B_XF+kc),0); if(i<7) rdy=chunk_mask(BAR(B_XF),c,lane,0); }
          const uint32_t da=dlo(sb+SM_XT+kc*16384+wg*8192,16), db=dlo(SLOT(2)+kc*8192,8192);
          FENCE();
#pragma unroll
          for(int kk=0;kk<4;kk++) wgmma_ss_n64_tb(acc,mkd(da+kk*2,dhi(1024,1)),mkd(db+kk*128,dhi(1024,1)),1);
          COMMIT();
        }
        WAITG(0); regfence(acc);
        if((tid&127)==0) mbar_arrive(BAR(B_QD));
        TS(1);
        mbar_wait(BAR(B_STAT),lp);
        uint32_t aq[16];
        {
          const int row=wg*64+w4*16+g;
          float2 s0=lds2(sb+SM_STAT+row*8), s1=lds2(sb+SM_STAT+row*8+64);
          const float sc=0.25f*1.4426950408889634f;
          s0.x*=sc; s0.y*=sc; s1.x*=sc; s1.y*=sc;
#pragma unroll
          for(int j=0;j<8;j++){
            float2 cs=lds2(sb+SM_CS+(192+8*j+2*t)*4);
            const float* a=&acc[4*j];
            aq[2*j]  =pack2(a[0]*s0.x-cs.x*s0.y,a[1]*s0.x-cs.y*s0.y);
            aq[2*j+1]=pack2(a[2]*s1.x-cs.x*s1.y,a[3]*s1.x-cs.y*s1.y);
          }
        }
        bar_sync(5,384);
#pragma unroll
        for(int h=0;h<4;h++) stsm4(TILE_ADDR(SLOT(1),h),aq[4*h],aq[4*h+1],aq[4*h+2],aq[4*h+3]);
        __syncwarp();
        bar_arrive(6,480); bar_arrive(15,288);
      } else {
        if(wg==3){
          uint32_t wk[32], wv[32];
          mbar_wait_u(BAR(B_WBKV),it);
          const uint32_t wa=SLOT(0)+w4*4096+(((lane&6)<<2)+(lane&1)+(lane>>4)*2)*32+((lane>>3)&1)*16;
#pragma unroll
          for(int ks=0;ks<8;ks++) ldsm4t(wa+(ks>>1)*1024+(ks&1)*128,wk[4*ks],wk[4*ks+1],wk[4*ks+2],wk[4*ks+3]);
          mbar_wait(BAR(B_GD),0); mbar_wait(BAR(B_XF+c),0);
          if(lane<2) poll_rlx(g_fx+(r*8+2*w4+lane)*32,EPOCH()*4+l);
          __syncwarp();
          TSR(tp);
          {
            float k0[4]={0,0,0,0},k1[4]={0,0,0,0},v0[4]={0,0,0,0},v1[4]={0,0,0,0};
            const unsigned char* xp=g_x+(size_t)(r*8+2*w4)*16384+(c*16+g)*128;
            uint4 xa[4], xb[4];
#pragma unroll
            for(int b=0;b<4;b++){ const unsigned char* q=xp+(b>>1)*16384+((((b&1)*4+t)^g)<<4); xa[b]=ld_rlx4(q); xb[b]=ld_rlx4(q+1024); }
            if(lane==0) mbar_arrive(BAR(B_LD));
#pragma unroll
            for(int ks=0;ks<8;ks++) ldsm4t(wa+16384+(ks>>1)*1024+(ks&1)*128,wv[4*ks],wv[4*ks+1],wv[4*ks+2],wv[4*ks+3]);
            bar_arrive(5,384);
#pragma unroll
            for(int ks=0;ks<8;ks++){
              const uint32_t b0=(ks&1)? xa[ks>>1].z : xa[ks>>1].x, b1=(ks&1)? xa[ks>>1].w : xa[ks>>1].y;
              const uint32_t b2=(ks&1)? xb[ks>>1].z : xb[ks>>1].x, b3=(ks&1)? xb[ks>>1].w : xb[ks>>1].y;
              mma16816(k0,wk[4*ks],wk[4*ks+1],wk[4*ks+2],wk[4*ks+3],b0,b1);
              mma16816(k1,wk[4*ks],wk[4*ks+1],wk[4*ks+2],wk[4*ks+3],b2,b3);
              mma16816(v0,wv[4*ks],wv[4*ks+1],wv[4*ks+2],wv[4*ks+3],b0,b1);
              mma16816(v1,wv[4*ks],wv[4*ks+1],wv[4*ks+2],wv[4*ks+3],b2,b3);
            }
            const int t2=fresh_tid();
            const uint32_t pw=SLOT(0)+(t2&96)*128+(t2&31)*16;
            sts4f(pw,k0[0],k0[1],k0[2],k0[3]); sts4f(pw+512,k1[0],k1[1],k1[2],k1[3]);
            sts4f(pw+1024,v0[0],v0[1],v0[2],v0[3]); sts4f(pw+1536,v1[0],v1[1],v1[2],v1[3]);
          }
          bar_sync(11,128);
          TSR(tm);
          IDS();
          if(w4<3){
            float acc[8]={0,0,0,0,0,0,0,0};
#pragma unroll
            for(int w=0;w<4;w++){
              const float4 a=lds4f(SLOT(0)+w*4096+(w4&1)*1024+lane*16), b=lds4f(SLOT(0)+w*4096+(w4&1)*1024+512+lane*16);
              acc[0]+=a.x; acc[1]+=a.y; acc[2]+=a.z; acc[3]+=a.w; acc[4]+=b.x; acc[5]+=b.y; acc[6]+=b.z; acc[7]+=b.w;
            }
            const unsigned ep=EPOCH();
            mbar_wait(BAR(B_STAT),lp);
            const float cs0=lds1(sb+SM_CSB+((w4&1)*16+g)*4), cs1=lds1(sb+SM_CSB+((w4&1)*16+g+8)*4);
            float kv[8];
#pragma unroll
            for(int j=0;j<2;j++){
              const float4 sa=lds4f(sb+SM_STAT+(c*16+8*j+2*t)*8);
              kv[2*j]=acc[4*j]*sa.x-cs0*sa.y;     kv[2*j+1]=acc[4*j+1]*sa.z-cs0*sa.w;
              kv[4+2*j]=acc[4*j+2]*sa.x-cs1*sa.y; kv[5+2*j]=acc[4*j+3]*sa.z-cs1*sa.w;
            }
            if(w4==2){
              float n[4];
#pragma unroll
              for(int k=0;k<4;k++){ n[k]=kv[k]*kv[k]+kv[4+k]*kv[4+k]; }
#pragma unroll
              for(int k=0;k<4;k++){ n[k]+=__shfl_xor_sync(~0u,n[k],4); n[k]+=__shfl_xor_sync(~0u,n[k],8); n[k]+=__shfl_xor_sync(~0u,n[k],16); }
              const unsigned nm=__reduce_max_sync(~0u,max(max(__float_as_uint(n[0]),__float_as_uint(n[1])),max(__float_as_uint(n[2]),__float_as_uint(n[3]))));
              if(lane==0) asm volatile("red.relaxed.gpu.global.max.u64 [%0], %1;"::"l"(g_kmax),"l"(((unsigned long long)(ep*2+it+1)<<32)|nm):"memory");
            } else {
              uint32_t d[4];
              if(w4==0){
                float a0=0.f,a1=0.f;
#pragma unroll
                for(int tt=0;tt<4;tt++){
                  float b0=a0,b1=a1; uint32_t e[4];
#pragma unroll
                  for(int k=0;k<4;k++){ e[k]=pack2(kv[k]-b0,kv[4+k]-b1); b0+=bflo(e[k]); b1+=bfhi(e[k]); }
                  if(t==tt){ d[0]=e[0]; d[1]=e[1]; d[2]=e[2]; d[3]=e[3]; }
                  if(tt<3){ a0=__shfl_sync(~0u,b0,(lane&28)+tt); a1=__shfl_sync(~0u,b1,(lane&28)+tt); }
                }
              } else {
#pragma unroll
                for(int k=0;k<4;k++) d[k]=pack2(kv[k],kv[4+k]);
              }
              const uint32_t t0=movm(prmt(d[0],d[1],0x5410)), t1=movm(prmt(d[0],d[1],0x7632));
              const uint32_t t2=movm(prmt(d[2],d[3],0x5410)), t3=movm(prmt(d[2],d[3],0x7632));
              const int i=bid&63; const uint32_t sw=((i>>2)&1)*16;
              unsigned char* kp=g_KV+w4*65536+((bid>>6)*16+4*(g>>1)+(g&1))*2048+i*32+t*4;
              *(uint32_t*)(kp+sw)=t0; *(uint32_t*)(kp+(sw^16))=t1; *(uint32_t*)(kp+4096+sw)=t2; *(uint32_t*)(kp+4096+(sw^16))=t3;
            }
            TSR(ti);
            asm volatile("fence.proxy.async.global;":::"memory");
            __syncwarp();
            bar_arrive(13,352);
            if(lane==0) red_rel(g_kc+r*32,1);
            bar_arrive(14,160);
            TS(3); TSW(2,tp); TSW(1,tm); TSW(4,ti);
          }
        } else if(warp==9){
          bar_sync(14,160);
          if(lane==0){ mbar_expect(BAR(B_RES),16384); bulk_ld(SLOT(0),g_x+(size_t)bid*16384,16384,BAR(B_RES)); }
          __syncwarp();
        } else if(warp==11){
          const int p=lane;
          const uint32_t k0= p==0? 0u : p==1? 3*2048u : p==2? 9*2048u : 17*2048u, k1= p==0? 3*2048u : p==1? 9*2048u : p==2? 17*2048u : 65536u;
          const uint32_t v0= p==0? 0u : k0-2048u, v1= p==3? 65536u : k1-2048u;
          if(lane<4) mbar_expect(BAR(B_KVF+p),(k1-k0)+(v1-v0)+(p==0?16:0));
          bar_sync(14,160);
          if(lane<16) poll_rlx(g_kc+lane*32,(EPOCH()*2+it+1)*24);
          __syncwarp();
          TS(10);
          mbar_wait_u(BAR(B_QD),it);
          if(p==0) bulk_ld(sb+SM_KMX,g_kmax,16,BAR(B_KVF));
#pragma unroll 1
          for(int j=0;j<4;j++){
            if(p==j){
              bulk_ld(sb+SM_XT+k0,g_KV+k0,k1-k0,BAR(B_KVF+p));
              bulk_ld(sb+SM_XT+65536+v0,g_KV+65536+v0,v1-v0,BAR(B_KVF+p));
            }
            __syncwarp();
          }
          if(lane<17) *(float4*)(g_kvacc+(it*8+c)*1088+r*68+lane*4)=make_float4(0.f,0.f,0.f,0.f);
          else if(lane<22 && it==0) *(float4*)(g_cs+c*320+r*20+(lane-17)*4)=make_float4(0.f,0.f,0.f,0.f);
          __syncwarp();
        }
        if(warp==11) bar_sync(15,288); else bar_sync(6,480);
      }
    }
    }
    if(lp==1){
      IDS();
      const uint32_t kd0=dlo(sb+SM_XT,16), vd0=dlo(sb+SM_XT+65536,65536);
#pragma unroll 1
      for(int tile=0;tile<2;tile++){
        uint32_t q0,q1,q2,q3;
        const uint32_t qa=TILE_ADDR(SLOT(1),(wg>>1)*2+tile);
        asm volatile("{.reg .pred p; setp.eq.u32 p, %0, 0;\n"
          "@p mbarrier.arrive.expect_tx.shared::cta.b64 _, [%3], 65536;\n"
          "@p cp.async.bulk.tensor.2d.shared::cluster.global.mbarrier::complete_tx::bytes [%1], [%2, {%4,%5}], [%3];\n"
          "@p cp.async.bulk.tensor.2d.shared::cluster.global.mbarrier::complete_tx::bytes [%1+16384], [%2, {%4,%6}], [%3];\n"
          "@p cp.async.bulk.tensor.2d.shared::cluster.global.mbarrier::complete_tx::bytes [%1+32768], [%2, {%4,%7}], [%3];\n"
          "@p cp.async.bulk.tensor.2d.shared::cluster.global.mbarrier::complete_tx::bytes [%1+49152], [%2, {%4,%8}], [%3];}"
          ::"r"(tid+1-tile),"r"(SLOT(2)),"l"(&maps.wob),"r"(BAR(B_WO)),"r"(c*64),"r"(0),"r"(128),"r"(256),"r"(384):"memory");
        ldsm4(qa,q0,q1,q2,q3);
        mbar_wait_u(BAR(B_KVF),it);
        if(tile==0) TS(11);
        bool ok, wide;
        {
          float n0=bflo(q0)*bflo(q0)+bfhi(q0)*bfhi(q0)+bflo(q2)*bflo(q2)+bfhi(q2)*bfhi(q2);
          float n1=bflo(q1)*bflo(q1)+bfhi(q1)*bfhi(q1)+bflo(q3)*bflo(q3)+bfhi(q3)*bfhi(q3);
          n0+=__shfl_xor_sync(~0u,n0,1); n0+=__shfl_xor_sync(~0u,n0,2);
          n1+=__shfl_xor_sync(~0u,n1,1); n1+=__shfl_xor_sync(~0u,n1,2);
          const float kmax2=lds1(sb+SM_KMX);
          wide=(n0*kmax2 <= BOUND2*BOUND2) && (n1*kmax2 <= BOUND2*BOUND2);
          ok=wg_all(8+wg,(n0*kmax2 <= BOUND*BOUND) && (n1*kmax2 <= BOUND*BOUND));
        }
        if(ok){ ok=att_tile<false>(q0,q1,q2,q3,qa,8+wg,kd0,vd0,BAR(B_KVF),it,cm1,cu); wide=false; }
        if(!ok) slow_tile(qa,8+wg,kd0,vd0,BAR(B_KVF),it,wide);
        TS(12+tile);
      }
      fence_async_smem();
      __syncthreads();
      TS(5);
    }

    {
    IDS();
    if(wg<2){
      float acc[32];
#pragma unroll
      for(int i=0;i<32;i++) acc[i]=0.f;
      regfence(acc);
      mbar_wait_u(BAR(B_WO),lp);
      uint32_t rdy=0;
#pragma unroll 1
      for(int i=0;i<8;i++){
        const int kc=(c+i)&7;
        if(!((rdy>>i)&1)){ mbar_wait_u(BAR(B_XF+kc),1); if(i<7) rdy=chunk_mask(BAR(B_XF),c,lane,1); }
        if(i==1) TS(6);
        const uint32_t da=dlo((i==0? SLOT(1) : sb+SM_XT+kc*16384)+wg*8192,16), db=dlo(SLOT(2)+kc*8192,8192);
        FENCE();
#pragma unroll
        for(int kk=0;kk<4;kk++) wgmma_ss_n64_tb(acc,mkd(da+kk*2,dhi(1024,1)),mkd(db+kk*128,dhi(1024,1)),1);
        COMMIT();
        if(i==0){ WAITG(0); if((tid&127)==0) mbar_arrive(BAR(B_F1)); }
      }
      if(lp) mbar_wait(BAR(B_RES),it);
      uint32_t rs[16];
#pragma unroll
      for(int h=0;h<4;h++) ldsm4(TILE_ADDR(lp? SLOT(0) : sb+SM_XT+c*16384,h),rs[4*h],rs[4*h+1],rs[4*h+2],rs[4*h+3]);
      WAITG(0); regfence(acc);
      if((tid&127)==0) mbar_arrive(BAR(B_GD));
      TSR(tg);
      uint32_t xn[16];
#pragma unroll
      for(int h=0;h<4;h++){
        const float* a=&acc[8*h];
        xn[4*h]  =pack2(a[0]+bflo(rs[4*h]),a[1]+bfhi(rs[4*h]));     xn[4*h+1]=pack2(a[2]+bflo(rs[4*h+1]),a[3]+bfhi(rs[4*h+1]));
        xn[4*h+2]=pack2(a[4]+bflo(rs[4*h+2]),a[5]+bfhi(rs[4*h+2])); xn[4*h+3]=pack2(a[6]+bflo(rs[4*h+3]),a[7]+bfhi(rs[4*h+3]));
        stsm4(TILE_ADDR(sb+SM_XT+c*16384,h),xn[4*h],xn[4*h+1],xn[4*h+2],xn[4*h+3]);
      }
      if(l<3){
        fence_async_smem();
        bar_arrive(12,288);
        TS(9);
        float s0=0,s1=0;
#pragma unroll
        for(int i=0;i<8;i++){ s0+=bflo(xn[2*i])+bfhi(xn[2*i]); s1+=bflo(xn[2*i+1])+bfhi(xn[2*i+1]); }
        s0+=__shfl_xor_sync(~0u,s0,1); s1+=__shfl_xor_sync(~0u,s1,1);
        s0+=__shfl_xor_sync(~0u,s0,2); s1+=__shfl_xor_sync(~0u,s1,2);
        const float m0=s0*(1.f/64), m1=s1*(1.f/64); float q0=0,q1=0;
#pragma unroll
        for(int i=0;i<8;i++){ float d;
          d=bflo(xn[2*i])-m0; q0+=d*d; d=bfhi(xn[2*i])-m0; q0+=d*d;
          d=bflo(xn[2*i+1])-m1; q1+=d*d; d=bfhi(xn[2*i+1])-m1; q1+=d*d; }
        q0+=__shfl_xor_sync(~0u,q0,1); q1+=__shfl_xor_sync(~0u,q1,1);
        q0+=__shfl_xor_sync(~0u,q0,2); q1+=__shfl_xor_sync(~0u,q1,2);
        if(t<2) st_rec(g_stat+bid*128+wg*64+w4*16+g+t*8,t? s1:s0,t? q1:q0,stat_tag(EPOCH()*4+l+1));
        __syncwarp();
        TS(8); TSW(7,tg);
      } else {
        TSW(7,tg);
        __syncwarp();
#pragma unroll
        for(int i=0;i<4;i++){
          const int row=wg*64+w4*16+i*4+(lane>>3);
          uint4 v=lds4u(sb+SM_XT+c*16384+row*128+(((lane&7)^(row&7))<<4));
          *(uint4*)(out+(size_t)(r*128+row)*512+c*64+(lane&7)*8)=v;
        }
      }
    } else if(warp==9){
      const unsigned tag=EPOCH()*4+l+1;
      if(lane==0){
        bulk_st(g_o+(size_t)bid*16384, SLOT(1), 16384);
        mbar_arrive(BAR(B_XF+c));
        bulk_wait();
        st_rlx(g_fo+bid*32, tag);
        if(lp==0){ mbar_expect(BAR(B_WBKV),16384); bulk_ld(SLOT(0),wbk,16384,BAR(B_WBKV)); }
        mbar_arrive(BAR(B_F1));
      }
      __syncwarp();
      TS(6);
      if(l<3){
        bar_sync(12,288);
        if(lane==0){
          bulk_st(g_x+(size_t)bid*16384, sb+SM_XT+c*16384, 16384);
          mbar_arrive(BAR(B_XF+c));
          bulk_wait();
          st_rlx(g_fx+bid*32, tag);
        }
        __syncwarp();
        TS(8);
      }
    } else if(warp==8){
      const unsigned tag=EPOCH()*4+l+1;
      const int kc=(c+lane)&7; const bool act=(lane>=1 && lane<8);
      {
        if(act) mbar_expect(BAR(B_XF+kc),16384);
        bool done=!act; int n=0;
        while(true){
          if(!done && (int)(ld_rlx(g_fo+(r*8+kc)*32)-tag)>=0){ bulk_ld(sb+SM_XT+kc*16384,g_o+(size_t)(r*8+kc)*16384,16384,BAR(B_XF+kc)); done=true; }
          if(__all_sync(~0u,done)) break;
          if(++n>(1<<21)) asm volatile("trap;");
        }
      }
      TS(6);
      if(l<3){
        if(lane==0){
          mbar_wait(BAR(B_F1),lp);
          if(lp==0){ mbar_expect(BAR(B_WBKV),16384); bulk_ld(SLOT(1),wbv,16384,BAR(B_WBKV)); }
          else { mbar_expect(BAR(B_WKV),16384); tma_wkv(SLOT(1),&maps.wkv,c*64,c*64,BAR(B_WKV)); }
        }
        __syncwarp();
        mbar_wait(BAR(B_GD),lp);
        if(act) mbar_expect(BAR(B_XF+kc),16384);
        if(lp==0) mbar_wait(BAR(B_LD),it);
        bool done=!act; int n=0;
        while(true){
          if(!done && (int)(ld_rlx(g_fx+(r*8+kc)*32)-tag)>=0){ bulk_ld(sb+SM_XT+kc*16384,g_x+(size_t)(r*8+kc)*16384,16384,BAR(B_XF+kc)); done=true; }
          if(__all_sync(~0u,done)) break;
          if(++n>(1<<21)) asm volatile("trap;");
        }
        TS(9);
      }
    } else if(warp==10){
      if(l<3 && lane==0){
        mbar_wait(BAR(B_GD),lp); mbar_wait(BAR(B_XF+c),0);
        if(lp==0){
          mbar_expect(BAR(B_WBQ),65536);
          mbar_wait(BAR(B_LD),it);
          for(int p=0;p<4;p++) tma2d(SLOT(2+p),&maps.wbq,c*64,p*128,BAR(B_WBQ));
        } else {
          for(int i=1;i<6;i++){ mbar_expect(BAR(B_WKV+i),16384); tma_wkv(WSLOT(i),&maps.wkv,c*64,((c+i)&7)*64,BAR(B_WKV+i)); }
        }
      }
      __syncwarp();
    }
    TS(14);
    }
  }
  if(bid==0 && threadIdx.x==0) *(volatile unsigned*)g_epoch = EPOCH()+1;
}

typedef CUresult (*EncFn)(CUtensorMap*, CUtensorMapDataType, cuuint32_t, void*, const cuuint64_t*, const cuuint64_t*, const cuuint32_t*, const cuuint32_t*,
                          CUtensorMapInterleave, CUtensorMapSwizzle, CUtensorMapL2promotion, CUtensorMapFloatOOBfill);
static void mk_map(EncFn f, CUtensorMap* m, const void* p, uint64_t cols, uint64_t rows, uint32_t bc, uint32_t br, CUtensorMapSwizzle sw){
  cuuint64_t dim[2]={cols,rows}; cuuint64_t str[1]={cols*2}; cuuint32_t box[2]={bc,br}; cuuint32_t es[2]={1,1};
  f(m,CU_TENSOR_MAP_DATA_TYPE_BFLOAT16,2,(void*)p,dim,str,box,es,CU_TENSOR_MAP_INTERLEAVE_NONE,sw,CU_TENSOR_MAP_L2_PROMOTION_L2_128B,CU_TENSOR_MAP_FLOAT_OOB_FILL_NONE);
}
extern "C" void kernel_launch(void* const* d_in, const int* in_sizes, int n_in, void* d_out, int out_size){
  static EncFn enc=nullptr;
  if(!enc){
    void* fn=nullptr; cudaDriverEntryPointQueryResult qr;
    cudaGetDriverEntryPoint("cuTensorMapEncodeTiled",&fn,cudaEnableDefault,&qr);
    enc=(EncFn)fn;
    cudaFuncSetAttribute(fused_kernel,cudaFuncAttributeMaxDynamicSharedMemorySize,SM_TOTAL);
  }
  Maps m;
  mk_map(enc,&m.x,  d_in[0],512,2048,64,128,CU_TENSOR_MAP_SWIZZLE_128B);
  {
    cuuint64_t dim[3]={512,512,3}; cuuint64_t str[2]={3072,1024}; cuuint32_t box[3]={64,64,2}; cuuint32_t es[3]={1,1,1};
    enc(&m.wkv,CU_TENSOR_MAP_DATA_TYPE_BFLOAT16,3,d_in[1],dim,str,box,es,CU_TENSOR_MAP_INTERLEAVE_NONE,CU_TENSOR_MAP_SWIZZLE_128B,CU_TENSOR_MAP_L2_PROMOTION_L2_128B,CU_TENSOR_MAP_FLOAT_OOB_FILL_NONE);
  }
  mk_map(enc,&m.wq, d_in[1],1536,512,64,128,CU_TENSOR_MAP_SWIZZLE_128B);
  mk_map(enc,&m.woa,d_in[2],512,512,64,128,CU_TENSOR_MAP_SWIZZLE_128B);
  mk_map(enc,&m.wbq,d_in[4],512,512,64,128,CU_TENSOR_MAP_SWIZZLE_128B);
  mk_map(enc,&m.wob,d_in[7],512,512,64,128,CU_TENSOR_MAP_SWIZZLE_128B);
  fused_kernel<<<128,512,SM_TOTAL>>>(m,(const unsigned char*)d_in[1],(const unsigned char*)d_in[2],(const unsigned char*)d_in[4],
      (const unsigned char*)d_in[5],(const unsigned char*)d_in[6],(const unsigned char*)d_in[7],(__nv_bfloat16*)d_out,0xffffffffu,0x9f809f80u);
}
```
